```python
import torch

def _softmax(x, axis=-1):
    return torch.softmax(x, dim=axis)
def _gelu(x):
    return torch.nn.functional.gelu(x, approximate="tanh")
def _silu(x):
    return torch.nn.functional.silu(x)
def _sigmoid(x):
    return torch.sigmoid(x)
def _layernorm(x, axis=-1, eps=1e-5):
    m = x.mean(dim=axis, keepdim=True)
    v = x.var(dim=axis, keepdim=True, unbiased=False)
    return (x - m) / torch.sqrt(v + eps)
def _scatter_add(tgt, idx, src, axis=0):
    return tgt.clone().index_add_(axis, idx, src)
def _segment_sum(src, seg, n):
    out = torch.zeros((n,) + src.shape[1:], dtype=src.dtype)
    return out.index_add_(0, seg, src)
def _pad(x, pw):
    flat = tuple(v for pair in reversed(pw) for v in pair)
    return torch.nn.functional.pad(x, flat)

kernel_name = 'standalone__mha_block_cached__decode'

def setup_inputs():

    _w = (lambda a: (lambda t: t.to(torch.bfloat16) if t.is_floating_point() else t)(torch.as_tensor(a)))
    B, Sq, D = 4, 1, 448
    H, Sk, Dh = 16, 8192, 256
    return {
        "x": _w((lambda *s: torch.randn(*s, dtype=torch.bfloat16) * 0.8)(B, Sq, D)),
        "k_cache": _w((lambda *s: torch.randn(*s, dtype=torch.bfloat16) * 0.8)(B, H, Sk, Dh)),
        "v_cache": _w((lambda *s: torch.randn(*s, dtype=torch.bfloat16) * 0.05)(B, H, Sk, Dh)),
        "wq": _w((lambda *s: torch.randn(*s, dtype=torch.bfloat16) * 0.8)(D, H * Dh) * (D ** -0.5)),
        "wo": _w((lambda *s: torch.randn(*s, dtype=torch.bfloat16) * 0.05)(H * Dh, D) * ((H * Dh) ** -0.5)),
    }

def reference(x, k_cache, v_cache, wq, wo):
    B, Sq, D = x.shape
    H, Dh = 16, 256
    q = (lambda x, *d: x.permute(*d))((x @ wq).reshape(B, Sq, H, Dh), 0, 2, 1, 3)
    scores = torch.einsum("bhqd,bhkd->bhqk", q, k_cache) * (Dh ** -0.5)
    p = _softmax(scores, axis=-1)
    o = torch.einsum("bhqk,bhkd->bhqd", p, v_cache)
    return (lambda x, *d: x.permute(*d))(o, 0, 2, 1, 3).reshape(B, Sq, H * Dh) @ wo
```

```cpp
#include <cuda_runtime.h>
#include <cuda_bf16.h>
#include <stdint.h>

namespace {

constexpr int NB = 4, NH = 16, SK = 8192, DH = 256, DM = 448;
constexpr int NBH = NB * NH;
constexpr int HD = NH * DH;

constexpr int CHUNK = 256;
constexpr int IPH = SK / CHUNK;
constexpr int NITEMS = NBH * IPH;
constexpr int TILE_KEYS = 32;
constexpr int TILE_BYTES = TILE_KEYS * DH * 2;
constexpr int TPI = CHUNK / TILE_KEYS;
constexpr int STAGES = 6;

constexpr int NCW = 8;
constexpr int NEW = 4;
constexpr int NTHREADS = (NCW + NEW + 1) * 32;
constexpr int KPW = CHUNK / NCW;
constexpr int NSREG = (KPW + 31) / 32;
static_assert(TILE_KEYS == 4 * NCW, "4 keys per warp per tile");
static_assert(IPH <= 64, "head merge handles up to 64 partials");

constexpr int QSLICES = HD / 32;
constexpr int OGROUPS = DM / 4;

struct __align__(128) Smem {
    uint8_t tiles[STAGES][TILE_BYTES];
    uint4 q[NBH * DH / 8];
    uint2 wo[HD];
    float red[2][NCW][DH];
    float xs[NB][DM];
    float red_ml[2][NCW][2];
    float fin[NCW][16];
    int red_item[2];
    int stage_item[STAGES];
    int last_flag;
    unsigned long long full[STAGES];
    unsigned long long empty[STAGES];
    unsigned long long red_full[2];
    unsigned long long red_empty[2];
};

__device__ __align__(16) __nv_bfloat16 g_q[NBH * DH];
__device__ __align__(16) float g_part[NITEMS * DH];
__device__ __align__(16) float2 g_part_ml[NITEMS];
__device__ __align__(16) __nv_bfloat16 g_o[NBH * DH];
__device__ unsigned int g_queue;
__device__ unsigned int g_qcount;
__device__ unsigned int g_done;
__device__ unsigned int g_headcnt[NBH];
__device__ unsigned int g_oflag[NBH];

__device__ __forceinline__ uint32_t smem_u32(const void* p) { return (uint32_t)__cvta_generic_to_shared(p); }
__device__ __forceinline__ void mbar_init(uint32_t bar, uint32_t cnt) {
    asm volatile("mbarrier.init.shared::cta.b64 [%0], %1;" ::"r"(bar), "r"(cnt) : "memory");
}
__device__ __forceinline__ void mbar_expect_tx(uint32_t bar, uint32_t bytes) {
    asm volatile("mbarrier.arrive.expect_tx.shared::cta.b64 _, [%0], %1;" ::"r"(bar), "r"(bytes) : "memory");
}
__device__ __forceinline__ void mbar_arrive(uint32_t bar) {
    asm volatile("mbarrier.arrive.shared::cta.b64 _, [%0];" ::"r"(bar) : "memory");
}
__device__ __forceinline__ bool mbar_try_wait(uint32_t bar, uint32_t parity) {
    uint32_t ok;
    asm volatile(
        "{\n.reg .pred p;\n"
        "mbarrier.try_wait.parity.shared::cta.b64 p, [%1], %2;\n"
        "selp.u32 %0, 1, 0, p;\n}\n"
        : "=r"(ok)
        : "r"(bar), "r"(parity)
        : "memory");
    return ok != 0;
}
__device__ __forceinline__ void mbar_wait(uint32_t bar, uint32_t parity) {
    if (mbar_try_wait(bar, parity)) return;
    uint32_t it = 0;
    while (!mbar_try_wait(bar, parity)) {
        if (++it > (1u << 24)) __trap();
    }
}
__device__ __forceinline__ void bulk_load(uint32_t dst, const void* src, uint32_t bytes, uint32_t bar) {
    asm volatile("cp.async.bulk.shared::cluster.global.mbarrier::complete_tx::bytes [%0], [%1], %2, [%3];"
                 ::"r"(dst), "l"(src), "r"(bytes), "r"(bar) : "memory");
}
__device__ __forceinline__ void named_bar(int id, int n) { asm volatile("bar.sync %0, %1;" ::"r"(id), "r"(n) : "memory"); }
__device__ __forceinline__ unsigned ld_acquire(const unsigned* p) {
    unsigned v;
    asm volatile("ld.acquire.gpu.global.u32 %0, [%1];" : "=r"(v) : "l"(p) : "memory");
    return v;
}
__device__ __forceinline__ void st_release(unsigned* p, unsigned v) {
    asm volatile("st.release.gpu.global.u32 [%0], %1;" ::"l"(p), "r"(v) : "memory");
}
__device__ __forceinline__ void spin_until(const unsigned* p, unsigned target) {
    uint32_t it = 0;
    while (ld_acquire(p) < target) {
        __nanosleep(32);
        if (++it > (1u << 24)) __trap();
    }
}
__device__ __forceinline__ float bf_lo(uint32_t u) { return __uint_as_float(u << 16); }
__device__ __forceinline__ float bf_hi(uint32_t u) { return __uint_as_float(u & 0xffff0000u); }
__device__ __forceinline__ float bf16_round(float x) { return __bfloat162float(__float2bfloat16_rn(x)); }
__device__ __forceinline__ uint4 ldg_nc(const void* p) {
    uint4 v;
    asm volatile("ld.global.nc.L1::no_allocate.v4.u32 {%0,%1,%2,%3}, [%4];"
                 : "=r"(v.x), "=r"(v.y), "=r"(v.z), "=r"(v.w) : "l"(p));
    return v;
}
__device__ __forceinline__ float ex2(float x) {
    float y;
    asm("ex2.approx.ftz.f32 %0, %1;" : "=f"(y) : "f"(x));
    return y;
}

__global__ void __launch_bounds__(NTHREADS, 1)
mha_decode_kernel(const __nv_bfloat16* __restrict__ x, const __nv_bfloat16* __restrict__ kc,
                  const __nv_bfloat16* __restrict__ vc, const __nv_bfloat16* __restrict__ wq,
                  const __nv_bfloat16* __restrict__ wo, __nv_bfloat16* __restrict__ out) {
    extern __shared__ __align__(128) uint8_t smem_raw[];
    Smem& sm = *reinterpret_cast<Smem*>(smem_raw);
    const int tid = threadIdx.x, warp = tid >> 5, lane = tid & 31;

    if (tid == 0) {
        for (int s = 0; s < STAGES; s++) {
            mbar_init(smem_u32(&sm.full[s]), 1);
            mbar_init(smem_u32(&sm.empty[s]), NCW);
        }
        for (int s = 0; s < 2; s++) {
            mbar_init(smem_u32(&sm.red_full[s]), NCW);
            mbar_init(smem_u32(&sm.red_empty[s]), NEW);
        }
        asm volatile("fence.mbarrier_init.release.cluster;" ::: "memory");
        asm volatile("fence.proxy.async.shared::cta;" ::: "memory");
    }
    __syncthreads();

    if (warp == NCW + NEW) {
        if (lane == 0) {
            int s = 0, ph = 1;
            int item = blockIdx.x;
            int next = NITEMS;
            while (true) {
                if (item >= NITEMS) {
                    mbar_wait(smem_u32(&sm.empty[s]), ph);
                    sm.stage_item[s] = -1;
                    mbar_arrive(smem_u32(&sm.full[s]));
                    break;
                }
                const uint8_t* ksrc = reinterpret_cast<const uint8_t*>(kc) + (size_t)item * (CHUNK * DH * 2);
                const uint8_t* vsrc = reinterpret_cast<const uint8_t*>(vc) + (size_t)item * (CHUNK * DH * 2);
#pragma unroll 1
                for (int t = 0; t < 2 * TPI; t++) {
                    if (t == TPI) next = (int)(atomicAdd(&g_queue, 1u) + gridDim.x);
                    mbar_wait(smem_u32(&sm.empty[s]), ph);
                    sm.stage_item[s] = item;
                    mbar_expect_tx(smem_u32(&sm.full[s]), TILE_BYTES);
                    const uint8_t* src = (t < TPI) ? ksrc + t * TILE_BYTES : vsrc + (t - TPI) * TILE_BYTES;
                    bulk_load(smem_u32(sm.tiles[s]), src, TILE_BYTES, smem_u32(&sm.full[s]));
                    if (++s == STAGES) { s = 0; ph ^= 1; }
                }
                item = next;
            }
        }
    } else if (warp >= NCW) {
        const int et = tid - NCW * 32;
        const int d = et * 2;
        int rb = 0, rph = 0;
        while (true) {
            mbar_wait(smem_u32(&sm.red_full[rb]), rph);
            const int item = sm.red_item[rb];
            if (item < 0) break;
            const int bh = item / IPH;
            float mw[NCW], M = -INFINITY;
#pragma unroll
            for (int w = 0; w < NCW; w++) { mw[w] = sm.red_ml[rb][w][0]; M = fmaxf(M, mw[w]); }
            float L = 0.f, o0 = 0.f, o1 = 0.f;
#pragma unroll
            for (int w = 0; w < NCW; w++) {
                const float sc = ex2(mw[w] - M);
                L += sc * sm.red_ml[rb][w][1];
                const float2 v = *reinterpret_cast<const float2*>(&sm.red[rb][w][d]);
                o0 += sc * v.x;
                o1 += sc * v.y;
            }
            __syncwarp();
            if (lane == 0) mbar_arrive(smem_u32(&sm.red_empty[rb]));
            *reinterpret_cast<float2*>(&g_part[(size_t)item * DH + d]) = make_float2(o0, o1);
            if (et == 0) g_part_ml[item] = make_float2(M, L);
            __threadfence();
            named_bar(2, NEW * 32);
            if (et == 0) {
                const unsigned old = atomicAdd(&g_headcnt[bh], 1u);
                sm.last_flag = (old == IPH - 1);
            }
            named_bar(2, NEW * 32);
            if (sm.last_flag) {
                __threadfence();
                float wgt[(IPH + 31) / 32];
                float Mh = -INFINITY;
                float2 ml[(IPH + 31) / 32];
#pragma unroll
                for (int i = 0; i < (IPH + 31) / 32; i++) {
                    const int c = i * 32 + lane;
                    ml[i] = (c < IPH) ? __ldcg(&g_part_ml[bh * IPH + c]) : make_float2(-INFINITY, 0.f);
                    Mh = fmaxf(Mh, ml[i].x);
                }
#pragma unroll
                for (int o = 16; o > 0; o >>= 1) Mh = fmaxf(Mh, __shfl_xor_sync(0xffffffffu, Mh, o));
                float Lh = 0.f;
#pragma unroll
                for (int i = 0; i < (IPH + 31) / 32; i++) {
                    wgt[i] = ex2(ml[i].x - Mh);
                    Lh += wgt[i] * ml[i].y;
                }
#pragma unroll
                for (int o = 16; o > 0; o >>= 1) Lh += __shfl_xor_sync(0xffffffffu, Lh, o);
                const float inv = 1.f / Lh;
                float a0 = 0.f, a1 = 0.f;
                const float* pp = &g_part[(size_t)bh * IPH * DH + d];
#pragma unroll
                for (int i = 0; i < (IPH + 31) / 32; i++) {
                    constexpr int N = IPH < 32 ? IPH : 32;
                    float2 v[N];
#pragma unroll
                    for (int c = 0; c < N; c++) v[c] = __ldcg(reinterpret_cast<const float2*>(pp + (size_t)(i * 32 + c) * DH));
#pragma unroll
                    for (int c = 0; c < N; c++) {
                        const float w = __shfl_sync(0xffffffffu, wgt[i], c);
                        a0 += w * v[c].x;
                        a1 += w * v[c].y;
                    }
                }
                *reinterpret_cast<__nv_bfloat162*>(&g_o[bh * DH + d]) = __floats2bfloat162_rn(a0 * inv, a1 * inv);
                __threadfence();
                named_bar(2, NEW * 32);
                if (et == 0) st_release(&g_oflag[bh], 1u);
            }
            rb ^= 1;
            if (rb == 0) rph ^= 1;
        }
    } else {
        {
            if (tid < NB * DM / 8) {
                const uint4 v = *reinterpret_cast<const uint4*>(x + tid * 8);
                float* dst = &sm.xs[0][0] + tid * 8;
                dst[0] = bf_lo(v.x); dst[1] = bf_hi(v.x); dst[2] = bf_lo(v.y); dst[3] = bf_hi(v.y);
                dst[4] = bf_lo(v.z); dst[5] = bf_hi(v.z); dst[6] = bf_lo(v.w); dst[7] = bf_hi(v.w);
            }
            float* qred = &sm.red[0][0][0];
            for (int slice = blockIdx.x; slice < QSLICES; slice += gridDim.x) {
                const int c4 = tid & 3, r0 = tid >> 2;
                uint4 w[7];
#pragma unroll
                for (int i = 0; i < 7; i++) w[i] = ldg_nc(wq + (size_t)(r0 + 64 * i) * HD + slice * 32 + c4 * 8);
                named_bar(1, NCW * 32);
                float acc[NB][8];
#pragma unroll
                for (int b = 0; b < NB; b++)
#pragma unroll
                    for (int j = 0; j < 8; j++) acc[b][j] = 0.f;
#pragma unroll
                for (int i = 0; i < 7; i++) {
                    const float f[8] = {bf_lo(w[i].x), bf_hi(w[i].x), bf_lo(w[i].y), bf_hi(w[i].y),
                                        bf_lo(w[i].z), bf_hi(w[i].z), bf_lo(w[i].w), bf_hi(w[i].w)};
#pragma unroll
                    for (int b = 0; b < NB; b++) {
                        const float xv = sm.xs[b][r0 + 64 * i];
#pragma unroll
                        for (int j = 0; j < 8; j++) acc[b][j] = fmaf(xv, f[j], acc[b][j]);
                    }
                }
#pragma unroll
                for (int b = 0; b < NB; b++)
#pragma unroll
                    for (int j = 0; j < 8; j++) {
                        float v = acc[b][j];
                        v += __shfl_xor_sync(0xffffffffu, v, 4);
                        v += __shfl_xor_sync(0xffffffffu, v, 8);
                        v += __shfl_xor_sync(0xffffffffu, v, 16);
                        acc[b][j] = v;
                    }
                if (lane < 4) {
#pragma unroll
                    for (int b = 0; b < NB; b++)
#pragma unroll
                        for (int j = 0; j < 8; j++) qred[(warp * NB + b) * 32 + lane * 8 + j] = acc[b][j];
                }
                named_bar(1, NCW * 32);
                if (tid < NB * 32) {
                    float v = 0.f;
#pragma unroll
                    for (int w2 = 0; w2 < NCW; w2++) v += qred[w2 * NB * 32 + tid];
                    const int b = tid >> 5, c = tid & 31;
                    g_q[b * HD + slice * 32 + c] = __float2bfloat16_rn(v);
                    __threadfence();
                }
                named_bar(1, NCW * 32);
                if (tid == 0) atomicAdd(&g_qcount, 1u);
            }
            if (blockIdx.x < OGROUPS) {
                uint2 w[16];
#pragma unroll
                for (int i = 0; i < 16; i++)
                    w[i] = __ldg(reinterpret_cast<const uint2*>(wo + (size_t)(i * 256 + tid) * DM + blockIdx.x * 4));
#pragma unroll
                for (int i = 0; i < 16; i++) sm.wo[i * 256 + tid] = w[i];
            }
            if (tid == 0) spin_until(&g_qcount, QSLICES);
            named_bar(1, NCW * 32);
            {
                uint4 v[8];
#pragma unroll
                for (int i = 0; i < 8; i++) v[i] = __ldcg(reinterpret_cast<const uint4*>(g_q) + i * 256 + tid);
#pragma unroll
                for (int i = 0; i < 8; i++) sm.q[i * 256 + tid] = v[i];
            }
            named_bar(1, NCW * 32);
        }

        const float SCL = 0.0625f * 1.4426950408889634f;
        const int g = lane >> 3, j = lane & 7;
        int s = 0, ph = 0, rb = 0, rph = 1;
        while (true) {
            mbar_wait(smem_u32(&sm.full[s]), ph);
            const int item = sm.stage_item[s];
            if (item < 0) break;
            const int bh = item / IPH;
            float qf[32];
#pragma unroll
            for (int i = 0; i < 4; i++) {
                const uint4 v = sm.q[bh * 32 + j + 8 * i];
                qf[i * 8 + 0] = bf_lo(v.x); qf[i * 8 + 1] = bf_hi(v.x);
                qf[i * 8 + 2] = bf_lo(v.y); qf[i * 8 + 3] = bf_hi(v.y);
                qf[i * 8 + 4] = bf_lo(v.z); qf[i * 8 + 5] = bf_hi(v.z);
                qf[i * 8 + 6] = bf_lo(v.w); qf[i * 8 + 7] = bf_hi(v.w);
            }
            float sc[NSREG];
#pragma unroll
            for (int i = 0; i < NSREG; i++) sc[i] = -INFINITY;
#pragma unroll
            for (int t = 0; t < TPI; t++) {
                if (t > 0) mbar_wait(smem_u32(&sm.full[s]), ph);
                const uint4* row = reinterpret_cast<const uint4*>(sm.tiles[s]) + (warp * 4 + g) * 32 + j;
                uint4 kv[4];
#pragma unroll
                for (int i = 0; i < 4; i++) kv[i] = row[8 * i];
                float a0 = 0.f, a1 = 0.f, a2 = 0.f, a3 = 0.f;
#pragma unroll
                for (int i = 0; i < 4; i++) {
                    a0 = fmaf(bf_lo(kv[i].x), qf[i * 8 + 0], a0);
                    a1 = fmaf(bf_hi(kv[i].x), qf[i * 8 + 1], a1);
                    a2 = fmaf(bf_lo(kv[i].y), qf[i * 8 + 2], a2);
                    a3 = fmaf(bf_hi(kv[i].y), qf[i * 8 + 3], a3);
                    a0 = fmaf(bf_lo(kv[i].z), qf[i * 8 + 4], a0);
                    a1 = fmaf(bf_hi(kv[i].z), qf[i * 8 + 5], a1);
                    a2 = fmaf(bf_lo(kv[i].w), qf[i * 8 + 6], a2);
                    a3 = fmaf(bf_hi(kv[i].w), qf[i * 8 + 7], a3);
                }
                float a = (a0 + a1) + (a2 + a3);
                __syncwarp();
                if (lane == 0) mbar_arrive(smem_u32(&sm.empty[s]));
                if (++s == STAGES) { s = 0; ph ^= 1; }
                a += __shfl_xor_sync(0xffffffffu, a, 1);
                a += __shfl_xor_sync(0xffffffffu, a, 2);
                a += __shfl_xor_sync(0xffffffffu, a, 4);
                const float v = __shfl_sync(0xffffffffu, a, (lane & 3) * 8);
                if ((lane >> 2) == (t & 7)) sc[t >> 3] = bf16_round(v) * SCL;
            }
            float m = sc[0];
#pragma unroll
            for (int i = 1; i < NSREG; i++) m = fmaxf(m, sc[i]);
#pragma unroll
            for (int o = 16; o > 0; o >>= 1) m = fmaxf(m, __shfl_xor_sync(0xffffffffu, m, o));
            float l = 0.f;
#pragma unroll
            for (int i = 0; i < NSREG; i++) { sc[i] = ex2(sc[i] - m); l += sc[i]; }
#pragma unroll
            for (int o = 16; o > 0; o >>= 1) l += __shfl_xor_sync(0xffffffffu, l, o);
            float acc[8];
#pragma unroll
            for (int i = 0; i < 8; i++) acc[i] = 0.f;
#pragma unroll
            for (int t = 0; t < TPI; t++) {
                mbar_wait(smem_u32(&sm.full[s]), ph);
                const uint4* row = reinterpret_cast<const uint4*>(sm.tiles[s]) + (warp * 4) * 32 + lane;
                uint4 vv[4];
#pragma unroll
                for (int i = 0; i < 4; i++) vv[i] = row[32 * i];
#pragma unroll
                for (int i = 0; i < 4; i++) {
                    const float p = __shfl_sync(0xffffffffu, sc[t >> 3], (t & 7) * 4 + i);
                    acc[0] = fmaf(p, bf_lo(vv[i].x), acc[0]);
                    acc[1] = fmaf(p, bf_hi(vv[i].x), acc[1]);
                    acc[2] = fmaf(p, bf_lo(vv[i].y), acc[2]);
                    acc[3] = fmaf(p, bf_hi(vv[i].y), acc[3]);
                    acc[4] = fmaf(p, bf_lo(vv[i].z), acc[4]);
                    acc[5] = fmaf(p, bf_hi(vv[i].z), acc[5]);
                    acc[6] = fmaf(p, bf_lo(vv[i].w), acc[6]);
                    acc[7] = fmaf(p, bf_hi(vv[i].w), acc[7]);
                }
                __syncwarp();
                if (lane == 0) mbar_arrive(smem_u32(&sm.empty[s]));
                if (++s == STAGES) { s = 0; ph ^= 1; }
            }
            mbar_wait(smem_u32(&sm.red_empty[rb]), rph);
            float4* dst = reinterpret_cast<float4*>(&sm.red[rb][warp][lane * 8]);
            dst[0] = make_float4(acc[0], acc[1], acc[2], acc[3]);
            dst[1] = make_float4(acc[4], acc[5], acc[6], acc[7]);
            if (lane == 0) {
                sm.red_ml[rb][warp][0] = m;
                sm.red_ml[rb][warp][1] = l;
                if (warp == 0) sm.red_item[rb] = item;
            }
            __syncwarp();
            if (lane == 0) mbar_arrive(smem_u32(&sm.red_full[rb]));
            rb ^= 1;
            if (rb == 0) rph ^= 1;
        }
        mbar_wait(smem_u32(&sm.red_empty[rb]), rph);
        if (lane == 0) {
            if (warp == 0) sm.red_item[rb] = -1;
            mbar_arrive(smem_u32(&sm.red_full[rb]));
        }

        for (int grp = blockIdx.x; grp < OGROUPS; grp += gridDim.x) {
            if (grp != (int)blockIdx.x) {
                named_bar(1, NCW * 32);
                for (int i = 0; i < 16; i++)
                    sm.wo[i * 256 + tid] = __ldg(reinterpret_cast<const uint2*>(wo + (size_t)(i * 256 + tid) * DM + grp * 4));
            }
            if (tid < NBH) spin_until(&g_oflag[tid], 1u);
            named_bar(1, NCW * 32);
            float acc[NB][4];
#pragma unroll
            for (int b = 0; b < NB; b++)
#pragma unroll
                for (int c = 0; c < 4; c++) acc[b][c] = 0.f;
            unsigned short ov[NBH];
#pragma unroll
            for (int i = 0; i < NBH; i++) ov[i] = __ldcg(reinterpret_cast<const unsigned short*>(g_o) + i * DH + tid);
#pragma unroll
            for (int h = 0; h < NH; h++) {
                const uint2 w = sm.wo[h * DH + tid];
                const float w0 = bf_lo(w.x), w1 = bf_hi(w.x), w2 = bf_lo(w.y), w3 = bf_hi(w.y);
#pragma unroll
                for (int b = 0; b < NB; b++) {
                    const float o = __uint_as_float((uint32_t)ov[b * NH + h] << 16);
                    acc[b][0] = fmaf(o, w0, acc[b][0]);
                    acc[b][1] = fmaf(o, w1, acc[b][1]);
                    acc[b][2] = fmaf(o, w2, acc[b][2]);
                    acc[b][3] = fmaf(o, w3, acc[b][3]);
                }
            }
#pragma unroll
            for (int b = 0; b < NB; b++)
#pragma unroll
                for (int c = 0; c < 4; c++) {
                    float v = acc[b][c];
#pragma unroll
                    for (int o = 16; o > 0; o >>= 1) v += __shfl_xor_sync(0xffffffffu, v, o);
                    if (lane == 0) sm.fin[warp][b * 4 + c] = v;
                }
            named_bar(1, NCW * 32);
            if (tid < 16) {
                float v = 0.f;
#pragma unroll
                for (int w2 = 0; w2 < NCW; w2++) v += sm.fin[w2][tid];
                out[(tid >> 2) * DM + grp * 4 + (tid & 3)] = __float2bfloat16_rn(v);
            }
        }
    }

    __syncthreads();
    if (tid == 0) {
        __threadfence();
        const unsigned old = atomicAdd(&g_done, 1u);
        if (old == gridDim.x - 1) {
            g_queue = 0;
            g_qcount = 0;
            for (int i = 0; i < NBH; i++) { g_headcnt[i] = 0; g_oflag[i] = 0; }
            __threadfence();
            g_done = 0;
        }
    }
}

}

extern "C" void kernel_launch(void* const* d_in, const int* in_sizes, int n_in, void* d_out, int out_size) {
    const __nv_bfloat16* x = (const __nv_bfloat16*)d_in[0];
    const __nv_bfloat16* kc = (const __nv_bfloat16*)d_in[1];
    const __nv_bfloat16* vc = (const __nv_bfloat16*)d_in[2];
    const __nv_bfloat16* wq = (const __nv_bfloat16*)d_in[3];
    const __nv_bfloat16* wo = (const __nv_bfloat16*)d_in[4];
    __nv_bfloat16* out = (__nv_bfloat16*)d_out;
    static int grid = 0;
    if (grid == 0) {
        int dev = 0, sms = 0;
        cudaGetDevice(&dev);
        cudaDeviceGetAttribute(&sms, cudaDevAttrMultiProcessorCount, dev);
        cudaFuncSetAttribute(mha_decode_kernel, cudaFuncAttributeMaxDynamicSharedMemorySize, (int)sizeof(Smem));
        grid = sms;
    }
    mha_decode_kernel<<<grid, NTHREADS, sizeof(Smem)>>>(x, kc, vc, wq, wo, out);
}
```

```cpp
#include <cuda_runtime.h>
#include <cuda_bf16.h>
#include <stdint.h>

namespace {

constexpr int NB = 4, NH = 16, SK = 8192, DH = 256, DM = 448;
constexpr int NBH = NB * NH;
constexpr int HD = NH * DH;

constexpr int TILE_KEYS = 32;
constexpr int TILE_BYTES = TILE_KEYS * DH * 2;
constexpr int STAGES = 4;
constexpr int DEPTH = 4;
constexpr int DEPTH_TAIL = 3;
static_assert(DEPTH <= STAGES && DEPTH_TAIL <= STAGES, "");

constexpr int C1 = 128, C2 = 64, C3 = 32, H1 = 60, H2 = 62;
constexpr int I1 = SK / C1, I2 = SK / C2, I3 = SK / C3;
constexpr int N1 = H1 * I1, N2 = N1 + (H2 - H1) * I2, NITEMS = N2 + (NBH - H2) * I3;
static_assert(C1 <= 256 && C3 >= TILE_KEYS && C1 % TILE_KEYS == 0 && C2 % TILE_KEYS == 0 && C3 % TILE_KEYS == 0, "");

constexpr int NCW = 8;
constexpr int NPW = 2;
constexpr int NEW = 4;
constexpr int NTHREADS = (NCW + NPW + NEW + 1) * 32;
static_assert(TILE_KEYS == 4 * NCW, "4 keys per warp per tile");

constexpr int QSLICES = HD / 32;
constexpr int OGROUPS = DM / 4;
constexpr int T1_MARGIN = 132, T2_MARGIN = 32, T3_MARGIN = 132;
constexpr int EB = NB - 1;
static_assert(EB * NH <= H1, "");
constexpr int FINE = 128;
constexpr int G2 = (H2 - H1) * DH / 4 / FINE;
constexpr int G3 = (NBH - H2) * DH / 4 / FINE;
static_assert(G2 >= 1 && G3 >= 1 && G2 <= 32 && G3 <= 32 && (G2 & (G2 - 1)) == 0 && (G3 & (G3 - 1)) == 0, "");
static_assert(I2 * G2 >= 128 && I3 * G3 >= 128 && I1 >= 8, "every merge thread needs at least one partial");

struct __align__(128) Smem {
    uint8_t tiles[STAGES][TILE_BYTES];
    uint4 qslot[STAGES][DH / 4];
    uint2 wo[HD];
    float red[2][NCW][DH];
    float xs[NB][DM];
    float mrg[NEW][32][5];
    float mrg_m[NEW];
    float red_ml[2][NCW][2];
    float fin[NCW][16];
    int red_item[2];
    unsigned tag;
    int progress;
    int stage_item[STAGES];
    unsigned long long full[STAGES];
    unsigned long long empty[STAGES];
    unsigned long long red_full[2];
    unsigned long long red_empty[2];
};

__device__ __align__(16) unsigned int g_q[NBH * DH];
__device__ __align__(16) unsigned int g_o[NBH * DH];
__device__ __align__(16) unsigned int g_part[NITEMS * DH];
__device__ __align__(16) uint2 g_part_ml[NITEMS];
__device__ unsigned int g_epoch;
__device__ unsigned int g_queue;
__device__ unsigned int g_done;


__device__ __forceinline__ uint32_t smem_u32(const void* p) { return (uint32_t)__cvta_generic_to_shared(p); }
__device__ __forceinline__ void mbar_init(uint32_t bar, uint32_t cnt) {
    asm volatile("mbarrier.init.shared::cta.b64 [%0], %1;" ::"r"(bar), "r"(cnt) : "memory");
}
__device__ __forceinline__ void mbar_expect_tx(uint32_t bar, uint32_t bytes) {
    asm volatile("mbarrier.arrive.expect_tx.shared::cta.b64 _, [%0], %1;" ::"r"(bar), "r"(bytes) : "memory");
}
__device__ __forceinline__ void mbar_arrive(uint32_t bar) {
    asm volatile("mbarrier.arrive.shared::cta.b64 _, [%0];" ::"r"(bar) : "memory");
}
__device__ __forceinline__ void release_after(uint32_t bar, float v, int lane, uint32_t rz) {
    const uint32_t dep = __ballot_sync(0xffffffffu, __float_as_uint(v) == 0x7fc12345u);
    if (lane == 0) mbar_arrive(bar + (dep & rz));
}
__device__ __forceinline__ bool mbar_try_wait(uint32_t bar, uint32_t parity) {
    uint32_t ok;
    asm volatile(
        "{\n.reg .pred p;\n"
        "mbarrier.try_wait.parity.shared::cta.b64 p, [%1], %2;\n"
        "selp.u32 %0, 1, 0, p;\n}\n"
        : "=r"(ok)
        : "r"(bar), "r"(parity)
        : "memory");
    return ok != 0;
}
__device__ __forceinline__ void mbar_wait(uint32_t bar, uint32_t parity) {
    if (mbar_try_wait(bar, parity)) return;
    uint32_t it = 0;
    while (!mbar_try_wait(bar, parity)) {
        if (++it > (1u << 24)) __trap();
    }
}
__device__ __forceinline__ void bulk_load(uint32_t dst, const void* src, uint32_t bytes, uint32_t bar) {
    asm volatile("cp.async.bulk.shared::cluster.global.mbarrier::complete_tx::bytes [%0], [%1], %2, [%3];"
                 ::"r"(dst), "l"(src), "r"(bytes), "r"(bar) : "memory");
}
__device__ __forceinline__ void bulk_load_hint(uint32_t dst, const void* src, uint32_t bytes, uint32_t bar, uint64_t pol) {
    asm volatile("cp.async.bulk.shared::cluster.global.mbarrier::complete_tx::bytes.L2::cache_hint [%0], [%1], %2, [%3], %4;"
                 ::"r"(dst), "l"(src), "r"(bytes), "r"(bar), "l"(pol) : "memory");
}
__device__ __forceinline__ void named_bar(int id, int n) { asm volatile("bar.sync %0, %1;" ::"r"(id), "r"(n) : "memory"); }
__device__ __forceinline__ unsigned ld_relaxed(const unsigned* p) {
    unsigned v;
    asm volatile("ld.relaxed.gpu.global.u32 %0, [%1];" : "=r"(v) : "l"(p) : "memory");
    return v;
}
__device__ __forceinline__ uint2 ld_relaxed2(const void* p) {
    uint2 v;
    asm volatile("ld.relaxed.gpu.global.v2.u32 {%0,%1}, [%2];" : "=r"(v.x), "=r"(v.y) : "l"(p) : "memory");
    return v;
}
__device__ __forceinline__ uint4 ld_relaxed4(const void* p) {
    uint4 v;
    asm volatile("ld.relaxed.gpu.global.v4.u32 {%0,%1,%2,%3}, [%4];" : "=r"(v.x), "=r"(v.y), "=r"(v.z), "=r"(v.w) : "l"(p) : "memory");
    return v;
}
__device__ __forceinline__ void st_relaxed(unsigned* p, unsigned v) {
    asm volatile("st.relaxed.gpu.global.u32 [%0], %1;" ::"l"(p), "r"(v) : "memory");
}
__device__ __forceinline__ void st_relaxed2(void* p, unsigned a, unsigned b) {
    asm volatile("st.relaxed.gpu.global.v2.u32 [%0], {%1, %2};" ::"l"(p), "r"(a), "r"(b) : "memory");
}
__device__ __forceinline__ void st_relaxed4(void* p, unsigned a, unsigned b, unsigned c, unsigned d) {
    asm volatile("st.relaxed.gpu.global.v4.u32 [%0], {%1, %2, %3, %4};" ::"l"(p), "r"(a), "r"(b), "r"(c), "r"(d) : "memory");
}
__device__ __forceinline__ unsigned atom_add_acq_rel(unsigned* p, unsigned v) {
    unsigned old;
    asm volatile("atom.acq_rel.gpu.global.add.u32 %0, [%1], %2;" : "=r"(old) : "l"(p), "r"(v) : "memory");
    return old;
}
__device__ __forceinline__ void backoff(uint32_t& it) {
    __nanosleep(40);
    if (++it > (1u << 24)) __trap();
}
__device__ __forceinline__ float bf_lo(uint32_t u) { return __uint_as_float(u << 16); }
__device__ __forceinline__ float bf_hi(uint32_t u) { return __uint_as_float(u & 0xffff0000u); }
__device__ __forceinline__ float bf16_round(float x) { return __bfloat162float(__float2bfloat16_rn(x)); }
__device__ __forceinline__ unsigned bf16_bits(float x) { return (unsigned)__bfloat16_as_ushort(__float2bfloat16_rn(x)); }
__device__ __forceinline__ uint4 ldg_nc(const void* p) {
    uint4 v;
    asm volatile("ld.global.nc.L1::no_allocate.v4.u32 {%0,%1,%2,%3}, [%4];"
                 : "=r"(v.x), "=r"(v.y), "=r"(v.z), "=r"(v.w) : "l"(p));
    return v;
}
__device__ __forceinline__ float ex2(float x) {
    float y;
    asm("ex2.approx.ftz.f32 %0, %1;" : "=f"(y) : "f"(x));
    return y;
}
__device__ __forceinline__ void item_info(int item, int& bh, int& row0, int& tpi) {
    if (item < N1) { bh = item / I1; row0 = item * C1; tpi = C1 / TILE_KEYS; }
    else if (item < N2) { const int r = item - N1; bh = H1 + r / I2; row0 = H1 * SK + r * C2; tpi = C2 / TILE_KEYS; }
    else { const int r = item - N2; bh = H2 + r / I3; row0 = H2 * SK + r * C3; tpi = C3 / TILE_KEYS; }
}
__device__ __forceinline__ void head_info(int bh, int& first, int& cnt) {
    if (bh < H1) { first = bh * I1; cnt = I1; }
    else if (bh < H2) { first = N1 + (bh - H1) * I2; cnt = I2; }
    else { first = N2 + (bh - H2) * I3; cnt = I3; }
}

template <int G, int BATCH>
__device__ __forceinline__ void merge_task(Smem& sm, int et, int bh, int dim0, unsigned tag) {
    constexpr int P = 128 / G;
    const unsigned tag2 = tag & 3u;
    const int lane = et & 31, ew = et >> 5;
    const int gi = et % G, pl = et / G;
    int first, cnt;
    head_info(bh, first, cnt);
    float M = -INFINITY, L = 0.f, a0 = 0.f, a1 = 0.f, a2 = 0.f, a3 = 0.f;
    for (int c0 = pl; c0 < cnt; c0 += P * BATCH) {
        uint4 v[BATCH];
        uint2 ml[BATCH];
#pragma unroll
        for (int i = 0; i < BATCH; i++) {
            const int c = first + c0 + P * i;
            v[i] = ld_relaxed4(&g_part[(size_t)c * DH + dim0 + gi * 4]);
            ml[i] = ld_relaxed2(&g_part_ml[c]);
        }
        uint32_t it = 0;
        while (true) {
            unsigned bad = 0;
#pragma unroll
            for (int i = 0; i < BATCH; i++)
                if (((v[i].x ^ tag2) | (v[i].y ^ tag2) | (v[i].z ^ tag2) | (v[i].w ^ tag2) | (ml[i].x ^ tag2) | (ml[i].y ^ tag2)) & 3u)
                    bad |= 1u << i;
            if (!__any_sync(0xffffffffu, bad != 0)) break;
            backoff(it);
#pragma unroll
            for (int i = 0; i < BATCH; i++)
                if (bad & (1u << i)) {
                    const int c = first + c0 + P * i;
                    v[i] = ld_relaxed4(&g_part[(size_t)c * DH + dim0 + gi * 4]);
                    ml[i] = ld_relaxed2(&g_part_ml[c]);
                }
        }
#pragma unroll
        for (int i = 0; i < BATCH; i++) {
            const float mc = __uint_as_float(ml[i].x & ~3u);
            const float Mn = fmaxf(M, mc);
            const float f0 = ex2(M - Mn), f1 = ex2(mc - Mn);
            L = L * f0 + __uint_as_float(ml[i].y & ~3u) * f1;
            a0 = a0 * f0 + __uint_as_float(v[i].x & ~3u) * f1;
            a1 = a1 * f0 + __uint_as_float(v[i].y & ~3u) * f1;
            a2 = a2 * f0 + __uint_as_float(v[i].z & ~3u) * f1;
            a3 = a3 * f0 + __uint_as_float(v[i].w & ~3u) * f1;
            M = Mn;
        }
    }
    float Mw = M;
#pragma unroll
    for (int o = 16; o > 0; o >>= 1) Mw = fmaxf(Mw, __shfl_xor_sync(0xffffffffu, Mw, o));
    named_bar(2, NEW * 32);
    if (lane == 0) sm.mrg_m[ew] = Mw;
    named_bar(2, NEW * 32);
    const float Mh = fmaxf(fmaxf(sm.mrg_m[0], sm.mrg_m[1]), fmaxf(sm.mrg_m[2], sm.mrg_m[3]));
    const float f = ex2(M - Mh);
    L *= f; a0 *= f; a1 *= f; a2 *= f; a3 *= f;
#pragma unroll
    for (int o = G; o < 32; o <<= 1) {
        L += __shfl_xor_sync(0xffffffffu, L, o);
        a0 += __shfl_xor_sync(0xffffffffu, a0, o);
        a1 += __shfl_xor_sync(0xffffffffu, a1, o);
        a2 += __shfl_xor_sync(0xffffffffu, a2, o);
        a3 += __shfl_xor_sync(0xffffffffu, a3, o);
    }
    if (lane < (G < 32 ? G : 32)) {
        float* dst = sm.mrg[ew][lane];
        dst[0] = L; dst[1] = a0; dst[2] = a1; dst[3] = a2; dst[4] = a3;
    }
    named_bar(2, NEW * 32);
    if (et < G) {
        float r[5] = {0.f, 0.f, 0.f, 0.f, 0.f};
        constexpr int STEP = G > 32 ? G / 32 : 1;
#pragma unroll
        for (int w = 0; w < NEW / STEP; w++) {
            const float* src = sm.mrg[w * STEP + (G > 32 ? ew : 0)][lane];
#pragma unroll
            for (int k = 0; k < 5; k++) r[k] += src[k];
        }
        const float inv = 1.f / r[0];
        st_relaxed4(&g_o[bh * DH + dim0 + et * 4], (bf16_bits(r[1] * inv) << 16) | tag, (bf16_bits(r[2] * inv) << 16) | tag,
                    (bf16_bits(r[3] * inv) << 16) | tag, (bf16_bits(r[4] * inv) << 16) | tag);
    }
}

__global__ void __launch_bounds__(NTHREADS, 1)
mha_decode_kernel(const __nv_bfloat16* __restrict__ x, const __nv_bfloat16* __restrict__ kc,
                  const __nv_bfloat16* __restrict__ vc, const __nv_bfloat16* __restrict__ wq,
                  const __nv_bfloat16* __restrict__ wo, __nv_bfloat16* __restrict__ out) {
    extern __shared__ __align__(128) uint8_t smem_raw[];
    Smem& sm = *reinterpret_cast<Smem*>(smem_raw);
    const int tid = threadIdx.x, warp = tid >> 5, lane = tid & 31;
    const uint32_t rz = gridDim.y - 1;

    uint4 wqv[7];
    uint4 xv4 = make_uint4(0, 0, 0, 0);
    if (warp < NCW) {
        if (blockIdx.x < QSLICES) {
#pragma unroll
            for (int i = 0; i < 7; i++)
                wqv[i] = ldg_nc(wq + (size_t)((tid >> 2) + 64 * i) * HD + blockIdx.x * 32 + (tid & 3) * 8);
        }
        if (tid < NB * DM / 8) xv4 = ldg_nc(x + tid * 8);
    }
    unsigned epoch = 0;
    if (tid == 32) epoch = ld_relaxed(&g_epoch);

    if (tid == 0) {
        for (int s = 0; s < STAGES; s++) {
            mbar_init(smem_u32(&sm.full[s]), 1);
            mbar_init(smem_u32(&sm.empty[s]), NCW);
        }
        for (int s = 0; s < 2; s++) {
            mbar_init(smem_u32(&sm.red_full[s]), NCW);
            mbar_init(smem_u32(&sm.red_empty[s]), NPW);
        }
        sm.progress = -1;
        asm volatile("fence.mbarrier_init.release.cluster;" ::: "memory");
        asm volatile("fence.proxy.async.shared::cta;" ::: "memory");
    }
    __syncthreads();

    if (warp == NCW + NPW + NEW) {
        if (lane == 0) {
            int s = 0;
            int n = 0;
            int item = blockIdx.x;
            uint64_t pol;
            asm volatile("createpolicy.fractional.L2::evict_first.b64 %0, 1.0;" : "=l"(pol));
            auto throttle = [&](int depth) {
                const int m = n - depth;
                if (m >= 0) mbar_wait(smem_u32(&sm.empty[m % STAGES]), (m / STAGES) & 1);
            };
            while (true) {
                if (item >= NITEMS) {
                    throttle(STAGES);
                    sm.stage_item[s] = -1;
                    mbar_arrive(smem_u32(&sm.full[s]));
                    if (atom_add_acq_rel(&g_done, 1u) == gridDim.x - 1) {
                        g_queue = 0;
                        g_epoch = sm.tag;
                        g_done = 0;
                    }
                    break;
                }
                int bh, row0, tpi;
                item_info(item, bh, row0, tpi);
                const uint8_t* ksrc = reinterpret_cast<const uint8_t*>(kc) + (size_t)row0 * (DH * 2);
                const uint8_t* vsrc = reinterpret_cast<const uint8_t*>(vc) + (size_t)row0 * (DH * 2);
                const int depth = item >= N2 ? DEPTH_TAIL : DEPTH;
                int next = NITEMS;
#pragma unroll 1
                for (int t = 0; t < 2 * tpi; t++) {
                    if (t == tpi) {
                        next = (int)(atomicAdd(&g_queue, 1u) + gridDim.x);
                        if (item == (int)blockIdx.x) {
                            constexpr int WO_BYTES = HD * DM * 2;
                            const int per = ((WO_BYTES / (int)gridDim.x) + 127) & ~127;
                            const int off = blockIdx.x * per;
                            const int nb = min(per, WO_BYTES - off);
                            if (nb > 0)
                                asm volatile("cp.async.bulk.prefetch.L2.global [%0], %1;"
                                             ::"l"(reinterpret_cast<const uint8_t*>(wo) + off), "r"(nb) : "memory");
                        }
                    }
                    throttle(depth);
                    sm.stage_item[s] = item;
                    const bool qcopy = (t == 0) && (item != (int)blockIdx.x);
                    mbar_expect_tx(smem_u32(&sm.full[s]), qcopy ? TILE_BYTES + DH * 4 : TILE_BYTES);
                    const uint8_t* src = (t < tpi) ? ksrc + t * TILE_BYTES : vsrc + (t - tpi) * TILE_BYTES;
                    bulk_load_hint(smem_u32(sm.tiles[s]), src, TILE_BYTES, smem_u32(&sm.full[s]), pol);
                    if (qcopy) bulk_load(smem_u32(sm.qslot[s]), &g_q[bh * DH], DH * 4, smem_u32(&sm.full[s]));
                    if (++s == STAGES) s = 0;
                    n++;
                }
                item = next;
            }
        }
    } else if (warp >= NCW + NPW) {
        const int et = tid - (NCW + NPW) * 32;
        auto wait_progress = [&](int target) {
            uint32_t it = 0;
            while (*reinterpret_cast<volatile int*>(&sm.progress) < target) {
                __nanosleep(200);
                if (++it > (1u << 24)) __trap();
            }
            __threadfence_block();
            __syncwarp();
        };
        wait_progress(0);
        const unsigned tag = sm.tag;
        if (blockIdx.x < OGROUPS) {
#pragma unroll 1
            for (int i0 = 0; i0 < HD / 128; i0 += 8) {
                uint2 w[8];
#pragma unroll
                for (int i = 0; i < 8; i++)
                    w[i] = __ldg(reinterpret_cast<const uint2*>(wo + (size_t)((i0 + i) * 128 + et) * DM + blockIdx.x * 4));
#pragma unroll
                for (int i = 0; i < 8; i++) sm.wo[(i0 + i) * 128 + et] = w[i];
            }
        }
        asm volatile("bar.arrive 3, %0;" ::"r"((NCW + NEW) * 32) : "memory");
        named_bar(2, NEW * 32);
        int task = blockIdx.x;
        for (; task < EB * NH * 4; task += gridDim.x) {
            wait_progress(((task >> 2) + 1) * I1 + (int)gridDim.x + T1_MARGIN);
            merge_task<16, (I1 < 64 ? I1 / 8 : 8)>(sm, et, task >> 2, (task & 3) * 64, tag);
        }
        wait_progress(EB * NH * I1 + (int)gridDim.x + T1_MARGIN);
        for (int grp = blockIdx.x; grp < OGROUPS; grp += gridDim.x) {
#pragma unroll 1
            for (int b = 0; b < EB; b++) {
                uint2 ov[NH];
                const unsigned* osrc = &g_o[b * NH * DH + et * 2];
#pragma unroll
                for (int h = 0; h < NH; h++) ov[h] = ld_relaxed2(osrc + h * DH);
                uint32_t it = 0;
                while (true) {
                    unsigned bad = 0;
#pragma unroll
                    for (int h = 0; h < NH; h++) bad |= (ov[h].x ^ tag) | (ov[h].y ^ tag);
                    if (!__any_sync(0xffffffffu, (bad & 0xffffu) != 0)) break;
                    backoff(it);
#pragma unroll
                    for (int h = 0; h < NH; h++)
                        if (((ov[h].x ^ tag) | (ov[h].y ^ tag)) & 0xffffu) ov[h] = ld_relaxed2(osrc + h * DH);
                }
                float acc[4] = {0.f, 0.f, 0.f, 0.f};
#pragma unroll
                for (int h = 0; h < NH; h++) {
                    uint2 wa, wb;
                    if (grp == (int)blockIdx.x) {
                        const uint4 w2 = *reinterpret_cast<const uint4*>(&sm.wo[h * DH + et * 2]);
                        wa = make_uint2(w2.x, w2.y); wb = make_uint2(w2.z, w2.w);
                    } else {
                        wa = __ldg(reinterpret_cast<const uint2*>(wo + (size_t)(h * DH + et * 2) * DM + grp * 4));
                        wb = __ldg(reinterpret_cast<const uint2*>(wo + (size_t)(h * DH + et * 2 + 1) * DM + grp * 4));
                    }
                    const float oa = bf_hi(ov[h].x), ob = bf_hi(ov[h].y);
                    acc[0] = fmaf(oa, bf_lo(wa.x), acc[0]); acc[1] = fmaf(oa, bf_hi(wa.x), acc[1]);
                    acc[2] = fmaf(oa, bf_lo(wa.y), acc[2]); acc[3] = fmaf(oa, bf_hi(wa.y), acc[3]);
                    acc[0] = fmaf(ob, bf_lo(wb.x), acc[0]); acc[1] = fmaf(ob, bf_hi(wb.x), acc[1]);
                    acc[2] = fmaf(ob, bf_lo(wb.y), acc[2]); acc[3] = fmaf(ob, bf_hi(wb.y), acc[3]);
                }
#pragma unroll
                for (int c = 0; c < 4; c++)
#pragma unroll
                    for (int o = 16; o > 0; o >>= 1) acc[c] += __shfl_xor_sync(0xffffffffu, acc[c], o);
                named_bar(2, NEW * 32);
                if (lane == 0) {
#pragma unroll
                    for (int c = 0; c < 4; c++) sm.mrg[et >> 5][0][c] = acc[c];
                }
                named_bar(2, NEW * 32);
                if (et < 4)
                    out[b * DM + grp * 4 + et] =
                        __float2bfloat16_rn((sm.mrg[0][0][et] + sm.mrg[1][0][et]) + (sm.mrg[2][0][et] + sm.mrg[3][0][et]));
            }
        }
        for (; task < H1 * 4; task += gridDim.x) {
            wait_progress(((task >> 2) + 1) * I1 + (int)gridDim.x + T1_MARGIN);
            merge_task<16, (I1 < 64 ? I1 / 8 : 8)>(sm, et, task >> 2, (task & 3) * 64, tag);
        }
        wait_progress(N2 + (int)gridDim.x + T2_MARGIN);
        for (task = blockIdx.x; task < FINE; task += gridDim.x)
            merge_task<G2, (I2 * G2 + 127) / 128>(sm, et, H1 + task / (FINE / (H2 - H1)), (task % (FINE / (H2 - H1))) * 4 * G2, tag);
        wait_progress(NITEMS - T3_MARGIN);
        for (task = blockIdx.x; task < FINE; task += gridDim.x)
            merge_task<G3, (I3 * G3 + 127) / 128>(sm, et, H2 + task / (FINE / (NBH - H2)), (task % (FINE / (NBH - H2))) * 4 * G3, tag);
    } else if (warp >= NCW) {
        const int pt = tid - NCW * 32;
        const int d = pt * 4;
        int rb = 0, rph = 0;
        while (true) {
            mbar_wait(smem_u32(&sm.red_full[rb]), rph);
            const unsigned tag2 = sm.tag & 3u;
            const int item = sm.red_item[rb];
            if (item < 0) break;
            float mw[NCW], M = -INFINITY;
#pragma unroll
            for (int w = 0; w < NCW; w++) { mw[w] = sm.red_ml[rb][w][0]; M = fmaxf(M, mw[w]); }
            M = __uint_as_float(__float_as_uint(M) & ~3u);
            float L = 0.f, o0 = 0.f, o1 = 0.f, o2 = 0.f, o3 = 0.f;
#pragma unroll
            for (int w = 0; w < NCW; w++) {
                const float sc = ex2(mw[w] - M);
                L += sc * sm.red_ml[rb][w][1];
                const float4 v = *reinterpret_cast<const float4*>(&sm.red[rb][w][d]);
                o0 += sc * v.x;
                o1 += sc * v.y;
                o2 += sc * v.z;
                o3 += sc * v.w;
            }
            release_after(smem_u32(&sm.red_empty[rb]), o0 + L, lane, rz);
            st_relaxed4(&g_part[(size_t)item * DH + d], (__float_as_uint(o0) & ~3u) | tag2, (__float_as_uint(o1) & ~3u) | tag2,
                        (__float_as_uint(o2) & ~3u) | tag2, (__float_as_uint(o3) & ~3u) | tag2);
            if (pt == 0) {
                st_relaxed2(&g_part_ml[item], (__float_as_uint(M) & ~3u) | tag2, (__float_as_uint(L) & ~3u) | tag2);
                __threadfence_block();
                *reinterpret_cast<volatile int*>(&sm.progress) = item;
            }
            rb ^= 1;
            if (rb == 0) rph ^= 1;
        }
        if (pt == 0) {
            __threadfence_block();
            *reinterpret_cast<volatile int*>(&sm.progress) = 0x7fffffff;
        }
    } else {
        unsigned tag;
        {
            if (tid < NB * DM / 8) {
                const uint4 v = xv4;
                float* dst = &sm.xs[0][0] + tid * 8;
                dst[0] = bf_lo(v.x); dst[1] = bf_hi(v.x); dst[2] = bf_lo(v.y); dst[3] = bf_hi(v.y);
                dst[4] = bf_lo(v.z); dst[5] = bf_hi(v.z); dst[6] = bf_lo(v.w); dst[7] = bf_hi(v.w);
            }
            if (tid == 32) sm.tag = (epoch & 0x7fffu) + 1u;
            named_bar(1, NCW * 32);
            tag = sm.tag;
            float* qred = &sm.red[0][0][0];
            for (int slice = blockIdx.x; slice < QSLICES; slice += gridDim.x) {
                const int c4 = tid & 3, r0 = tid >> 2;
                uint4 w[7];
#pragma unroll
                for (int i = 0; i < 7; i++)
                    w[i] = (slice == (int)blockIdx.x) ? wqv[i] : ldg_nc(wq + (size_t)(r0 + 64 * i) * HD + slice * 32 + c4 * 8);
                if (slice != (int)blockIdx.x) named_bar(1, NCW * 32);
                float acc[NB][8];
#pragma unroll
                for (int b = 0; b < NB; b++)
#pragma unroll
                    for (int j = 0; j < 8; j++) acc[b][j] = 0.f;
#pragma unroll
                for (int i = 0; i < 7; i++) {
                    const float f[8] = {bf_lo(w[i].x), bf_hi(w[i].x), bf_lo(w[i].y), bf_hi(w[i].y),
                                        bf_lo(w[i].z), bf_hi(w[i].z), bf_lo(w[i].w), bf_hi(w[i].w)};
#pragma unroll
                    for (int b = 0; b < NB; b++) {
                        const float xv = sm.xs[b][r0 + 64 * i];
#pragma unroll
                        for (int j = 0; j < 8; j++) acc[b][j] = fmaf(xv, f[j], acc[b][j]);
                    }
                }
#pragma unroll
                for (int b = 0; b < NB; b++)
#pragma unroll
                    for (int j = 0; j < 8; j++) {
                        float v = acc[b][j];
                        v += __shfl_xor_sync(0xffffffffu, v, 4);
                        v += __shfl_xor_sync(0xffffffffu, v, 8);
                        v += __shfl_xor_sync(0xffffffffu, v, 16);
                        acc[b][j] = v;
                    }
                if (lane < 4) {
#pragma unroll
                    for (int b = 0; b < NB; b++)
#pragma unroll
                        for (int j = 0; j < 8; j++) qred[(warp * NB + b) * 32 + lane * 8 + j] = acc[b][j];
                }
                named_bar(1, NCW * 32);
                if (tid < NB * 32) {
                    float v = 0.f;
#pragma unroll
                    for (int w2 = 0; w2 < NCW; w2++) v += qred[w2 * NB * 32 + tid];
                    const int b = tid >> 5, c = tid & 31;
                    st_relaxed(&g_q[b * HD + slice * 32 + c], (bf16_bits(v) << 16) | tag);
                }
            }
        }

        const float SCL = 0.0625f * 1.4426950408889634f;
        const int g = lane >> 3, j = lane & 7;
        int s = 0, ph = 0, rb = 0, rph = 1;
        while (true) {
            mbar_wait(smem_u32(&sm.full[s]), ph);
            const int item = sm.stage_item[s];
            if (item < 0) break;
            int bh, row0, tpi;
            item_info(item, bh, row0, tpi);
            float qf[32];
            {
                uint4 qa[8];
                if (item != (int)blockIdx.x) {
#pragma unroll
                    for (int i = 0; i < 4; i++) {
                        qa[2 * i] = sm.qslot[s][(j + 8 * i) * 2];
                        qa[2 * i + 1] = sm.qslot[s][(j + 8 * i) * 2 + 1];
                    }
                } else {
#pragma unroll
                    for (int i = 0; i < 8; i++) qa[i] = make_uint4(~tag, ~tag, ~tag, ~tag);
                }
                uint32_t it = 0;
                while (true) {
                    unsigned bad = 0;
#pragma unroll
                    for (int i = 0; i < 8; i++) bad |= (qa[i].x ^ tag) | (qa[i].y ^ tag) | (qa[i].z ^ tag) | (qa[i].w ^ tag);
                    if (!__any_sync(0xffffffffu, (bad & 0xffffu) != 0)) break;
                    if (it) backoff(it); else it = 1;
#pragma unroll
                    for (int i = 0; i < 4; i++) {
                        qa[2 * i] = ld_relaxed4(&g_q[bh * DH + (j + 8 * i) * 8]);
                        qa[2 * i + 1] = ld_relaxed4(&g_q[bh * DH + (j + 8 * i) * 8 + 4]);
                    }
                }
#pragma unroll
                for (int i = 0; i < 8; i++) {
                    qf[i * 4 + 0] = bf_hi(qa[i].x); qf[i * 4 + 1] = bf_hi(qa[i].y);
                    qf[i * 4 + 2] = bf_hi(qa[i].z); qf[i * 4 + 3] = bf_hi(qa[i].w);
                }
            }
            float sc = -INFINITY;
#pragma unroll 2
            for (int t = 0; t < tpi; t++) {
                if (t > 0) mbar_wait(smem_u32(&sm.full[s]), ph);
                const uint4* row = reinterpret_cast<const uint4*>(sm.tiles[s]) + (warp * 4 + g) * 32 + j;
                uint4 kv[4];
#pragma unroll
                for (int i = 0; i < 4; i++) kv[i] = row[8 * i];
                float a0 = 0.f, a1 = 0.f, a2 = 0.f, a3 = 0.f;
#pragma unroll
                for (int i = 0; i < 4; i++) {
                    a0 = fmaf(bf_lo(kv[i].x), qf[i * 8 + 0], a0);
                    a1 = fmaf(bf_hi(kv[i].x), qf[i * 8 + 1], a1);
                    a2 = fmaf(bf_lo(kv[i].y), qf[i * 8 + 2], a2);
                    a3 = fmaf(bf_hi(kv[i].y), qf[i * 8 + 3], a3);
                    a0 = fmaf(bf_lo(kv[i].z), qf[i * 8 + 4], a0);
                    a1 = fmaf(bf_hi(kv[i].z), qf[i * 8 + 5], a1);
                    a2 = fmaf(bf_lo(kv[i].w), qf[i * 8 + 6], a2);
                    a3 = fmaf(bf_hi(kv[i].w), qf[i * 8 + 7], a3);
                }
                float a = (a0 + a1) + (a2 + a3);
                release_after(smem_u32(&sm.empty[s]), a, lane, rz);
                if (++s == STAGES) { s = 0; ph ^= 1; }
                a += __shfl_xor_sync(0xffffffffu, a, 1);
                a += __shfl_xor_sync(0xffffffffu, a, 2);
                a += __shfl_xor_sync(0xffffffffu, a, 4);
                const float v = __shfl_sync(0xffffffffu, a, (lane & 3) * 8);
                if ((lane >> 2) == t) sc = bf16_round(v) * SCL;
            }
            float m = sc;
#pragma unroll
            for (int o = 16; o > 0; o >>= 1) m = fmaxf(m, __shfl_xor_sync(0xffffffffu, m, o));
            sc = ex2(sc - m);
            float l = sc;
#pragma unroll
            for (int o = 16; o > 0; o >>= 1) l += __shfl_xor_sync(0xffffffffu, l, o);
            float acc[8];
#pragma unroll
            for (int i = 0; i < 8; i++) acc[i] = 0.f;
#pragma unroll 2
            for (int t = 0; t < tpi; t++) {
                mbar_wait(smem_u32(&sm.full[s]), ph);
                const uint4* row = reinterpret_cast<const uint4*>(sm.tiles[s]) + (warp * 4) * 32 + lane;
                uint4 vv[4];
#pragma unroll
                for (int i = 0; i < 4; i++) vv[i] = row[32 * i];
#pragma unroll
                for (int i = 0; i < 4; i++) {
                    const float p = __shfl_sync(0xffffffffu, sc, t * 4 + i);
                    acc[0] = fmaf(p, bf_lo(vv[i].x), acc[0]);
                    acc[1] = fmaf(p, bf_hi(vv[i].x), acc[1]);
                    acc[2] = fmaf(p, bf_lo(vv[i].y), acc[2]);
                    acc[3] = fmaf(p, bf_hi(vv[i].y), acc[3]);
                    acc[4] = fmaf(p, bf_lo(vv[i].z), acc[4]);
                    acc[5] = fmaf(p, bf_hi(vv[i].z), acc[5]);
                    acc[6] = fmaf(p, bf_lo(vv[i].w), acc[6]);
                    acc[7] = fmaf(p, bf_hi(vv[i].w), acc[7]);
                }
                release_after(smem_u32(&sm.empty[s]), acc[0], lane, rz);
                if (++s == STAGES) { s = 0; ph ^= 1; }
            }
            mbar_wait(smem_u32(&sm.red_empty[rb]), rph);
            float4* dst = reinterpret_cast<float4*>(&sm.red[rb][warp][lane * 8]);
            dst[0] = make_float4(acc[0], acc[1], acc[2], acc[3]);
            dst[1] = make_float4(acc[4], acc[5], acc[6], acc[7]);
            if (lane == 0) {
                sm.red_ml[rb][warp][0] = m;
                sm.red_ml[rb][warp][1] = l;
                if (warp == 0) sm.red_item[rb] = item;
            }
            __syncwarp();
            if (lane == 0) mbar_arrive(smem_u32(&sm.red_full[rb]));
            rb ^= 1;
            if (rb == 0) rph ^= 1;
        }
        mbar_wait(smem_u32(&sm.red_empty[rb]), rph);
        if (lane == 0) {
            if (warp == 0) sm.red_item[rb] = -1;
            mbar_arrive(smem_u32(&sm.red_full[rb]));
        }

        named_bar(3, (NCW + NEW) * 32);

        for (int grp = blockIdx.x; grp < OGROUPS; grp += gridDim.x) {
            uint2 wv[NH];
#pragma unroll
            for (int h = 0; h < NH; h++)
                wv[h] = (grp == (int)blockIdx.x) ? sm.wo[h * DH + tid]
                                                 : __ldg(reinterpret_cast<const uint2*>(wo + (size_t)(h * DH + tid) * DM + grp * 4));
            if (grp != (int)blockIdx.x) named_bar(1, NCW * 32);
            {
                unsigned ov[NH];
                const unsigned* osrc = &g_o[EB * NH * DH + tid];
#pragma unroll
                for (int i = 0; i < NH; i++) ov[i] = ld_relaxed(osrc + i * DH);
                uint32_t it = 0;
                while (true) {
                    unsigned bad = 0;
#pragma unroll
                    for (int i = 0; i < NH; i++) bad |= ov[i] ^ tag;
                    if (!__any_sync(0xffffffffu, (bad & 0xffffu) != 0)) break;
                    backoff(it);
#pragma unroll
                    for (int i = 0; i < NH; i++)
                        if ((ov[i] & 0xffffu) != tag) ov[i] = ld_relaxed(osrc + i * DH);
                }
                float acc[4] = {0.f, 0.f, 0.f, 0.f};
#pragma unroll
                for (int h = 0; h < NH; h++) {
                    const float oa = bf_hi(ov[h]);
                    acc[0] = fmaf(oa, bf_lo(wv[h].x), acc[0]); acc[1] = fmaf(oa, bf_hi(wv[h].x), acc[1]);
                    acc[2] = fmaf(oa, bf_lo(wv[h].y), acc[2]); acc[3] = fmaf(oa, bf_hi(wv[h].y), acc[3]);
                }
#pragma unroll
                for (int c = 0; c < 2; c++) {
                    const bool up = lane & 16;
                    const float send = up ? acc[c] : acc[c + 2];
                    const float keep = up ? acc[c + 2] : acc[c];
                    acc[c] = keep + __shfl_xor_sync(0xffffffffu, send, 16);
                }
                {
                    const bool up = lane & 8;
                    const float send = up ? acc[0] : acc[1];
                    const float keep = up ? acc[1] : acc[0];
                    acc[0] = keep + __shfl_xor_sync(0xffffffffu, send, 8);
                }
                acc[0] += __shfl_xor_sync(0xffffffffu, acc[0], 4);
                acc[0] += __shfl_xor_sync(0xffffffffu, acc[0], 2);
                acc[0] += __shfl_xor_sync(0xffffffffu, acc[0], 1);
                if ((lane & 7) == 0) sm.fin[warp][lane >> 3] = acc[0];
            }
            named_bar(1, NCW * 32);
            if (tid < 4) {
                float v = 0.f;
#pragma unroll
                for (int w2 = 0; w2 < NCW; w2++) v += sm.fin[w2][tid];
                out[EB * DM + grp * 4 + tid] = __float2bfloat16_rn(v);
            }
        }
    }

}

}

extern "C" void kernel_launch(void* const* d_in, const int* in_sizes, int n_in, void* d_out, int out_size) {
    const __nv_bfloat16* x = (const __nv_bfloat16*)d_in[0];
    const __nv_bfloat16* kc = (const __nv_bfloat16*)d_in[1];
    const __nv_bfloat16* vc = (const __nv_bfloat16*)d_in[2];
    const __nv_bfloat16* wq = (const __nv_bfloat16*)d_in[3];
    const __nv_bfloat16* wo = (const __nv_bfloat16*)d_in[4];
    __nv_bfloat16* out = (__nv_bfloat16*)d_out;
    static int grid = 0;
    if (grid == 0) {
        int dev = 0, sms = 0;
        cudaGetDevice(&dev);
        cudaDeviceGetAttribute(&sms, cudaDevAttrMultiProcessorCount, dev);
        cudaFuncSetAttribute(mha_decode_kernel, cudaFuncAttributeMaxDynamicSharedMemorySize, (int)sizeof(Smem));
        grid = sms;
    }
    mha_decode_kernel<<<grid, NTHREADS, sizeof(Smem)>>>(x, kc, vc, wq, wo, out);
}
```
